```python
import torch

def _softmax(x, axis=-1):
    return torch.softmax(x, dim=axis)
def _gelu(x):
    return torch.nn.functional.gelu(x, approximate="tanh")
def _silu(x):
    return torch.nn.functional.silu(x)
def _sigmoid(x):
    return torch.sigmoid(x)
def _layernorm(x, axis=-1, eps=1e-5):
    m = x.mean(dim=axis, keepdim=True)
    v = x.var(dim=axis, keepdim=True, unbiased=False)
    return (x - m) / torch.sqrt(v + eps)
def _scatter_add(tgt, idx, src, axis=0):
    return tgt.clone().index_add_(axis, idx, src)
def _segment_sum(src, seg, n):
    out = torch.zeros((n,) + src.shape[1:], dtype=src.dtype)
    return out.index_add_(0, seg, src)
def _pad(x, pw):
    flat = tuple(v for pair in reversed(pw) for v in pair)
    return torch.nn.functional.pad(x, flat)

kernel_name = 'recurrent_scan__ssm_conv_s5__glu_gated_reglu__prompt'

def setup_inputs():

    _w = (lambda a: (lambda t: t.to(torch.bfloat16) if t.is_floating_point() else t)(torch.as_tensor(a)))
    def _A_setup():
        B, S, D = 1, 2048, 512
        P = D
        Lambda_re = -0.5 * (lambda _x: torch.exp(torch.as_tensor(_x)))((lambda *s: torch.randn(*s, dtype=torch.bfloat16) * 0.8)(P))
        Lambda_im = (lambda *s: torch.randn(*s, dtype=torch.bfloat16) * 0.8)(P) * 1.0
        B_re = (lambda *s: torch.randn(*s, dtype=torch.bfloat16) * 0.8)(P, D) * (D ** -0.5)
        B_im = (lambda *s: torch.randn(*s, dtype=torch.bfloat16) * 0.8)(P, D) * (D ** -0.5)
        C_re = (lambda *s: torch.randn(*s, dtype=torch.bfloat16) * 0.8)(D, P) * (P ** -0.5)
        C_im = (lambda *s: torch.randn(*s, dtype=torch.bfloat16) * 0.8)(D, P) * (P ** -0.5)
        log_dt = (lambda *s: torch.randn(*s, dtype=torch.bfloat16) * 0.8)(P) * 0.3 - 2.0
        Dskip = (lambda *s: torch.randn(*s, dtype=torch.bfloat16) * 0.8)(D)
        return {
            "x": _w((lambda *s: torch.randn(*s, dtype=torch.bfloat16) * 0.05)(B, S, D)),
            "Lambda_re": _w(Lambda_re),
            "Lambda_im": _w(Lambda_im),
            "B_re": _w(B_re),
            "B_im": _w(B_im),
            "C_re": _w(C_re),
            "C_im": _w(C_im),
            "log_dt": _w(log_dt),
            "Dskip": _w(Dskip),
        }
    _A_in = _A_setup()

    def _B_setup():
        B, S, D, F = 1, 2048, 512, 1376
        return {
            "x": _w((lambda *s: torch.randn(*s, dtype=torch.bfloat16) * 0.05)(B, S, D)),
            "W_gate": _w((lambda *s: torch.randn(*s, dtype=torch.bfloat16) * 0.2)(D, F) * (2.0 / D) ** 0.5),
            "W_up": _w((lambda *s: torch.randn(*s, dtype=torch.bfloat16) * 0.2)(D, F) * (2.0 / D) ** 0.5),
            "W_down": _w((lambda *s: torch.randn(*s, dtype=torch.bfloat16) * 0.2)(F, D) * (1.0 / F) ** 0.5),
        }
    _B_in = _B_setup()

    return {
        "A_x": _A_in["x"],
        "A_Lambda_re": _A_in["Lambda_re"],
        "A_Lambda_im": _A_in["Lambda_im"],
        "A_B_re": _A_in["B_re"],
        "A_B_im": _A_in["B_im"],
        "A_C_re": _A_in["C_re"],
        "A_C_im": _A_in["C_im"],
        "A_log_dt": _A_in["log_dt"],
        "A_Dskip": _A_in["Dskip"],
        "B_x": _B_in["x"],
        "B_W_gate": _B_in["W_gate"],
        "B_W_up": _B_in["W_up"],
        "B_W_down": _B_in["W_down"],
    }

def reference(A_x, A_Lambda_re, A_Lambda_im, A_B_re, A_B_im, A_C_re, A_C_im, A_log_dt, A_Dskip, B_x, B_W_gate, B_W_up, B_W_down):
    def _A_ref(x, Lambda_re, Lambda_im, B_re, B_im, C_re, C_im, log_dt, Dskip):
        Bsz, L, H = x.shape
        Lam = Lambda_re + 1j * Lambda_im
        Bmat = B_re + 1j * B_im
        Cmat = C_re + 1j * C_im
        dt = torch.exp(log_dt)
        Lam_bar = torch.exp(dt * Lam)
        B_bar = ((Lam_bar - 1.0) / Lam)[:, None] * Bmat
        Bu = torch.einsum("bld,pd->blp", x + 0j, B_bar)
        h = torch.zeros_like(Bu[:, 0, :])
        hs = []
        for t in range(L):
            h = Lam_bar[None, :] * h + Bu[:, t, :]
            hs.append(h)
        hseq = torch.stack(hs, 1)
        y = 2.0 * torch.einsum("blp,dp->bld", hseq, Cmat).real + x * Dskip[None, None, :]
        return y

    def _B_ref(x, W_gate, W_up, W_down):
        gate = torch.einsum("bsd,df->bsf", x, W_gate)
        up = torch.einsum("bsd,df->bsf", x, W_up)
        gate = gate * (lambda x, dt: x.to(dt))(gate > 0, gate.dtype)
        h = gate * up
        return torch.einsum("bsf,fd->bsd", h, W_down)

    x = A_x
    xn = _layernorm(x, axis=-1)
    s = _A_ref(xn, A_Lambda_re, A_Lambda_im, A_B_re, A_B_im, A_C_re, A_C_im, A_log_dt, A_Dskip)
    g = _silu(_B_ref(xn, B_W_gate, B_W_up, B_W_down))
    return x + s * g
```

```cpp
#include <cuda_runtime.h>
#include <cuda_bf16.h>
#include <cuda.h>
#include <stdint.h>

namespace {

constexpr int D_ = 512, F_ = 1376;
constexpr int SLOT = 16384;
constexpr int SL_ST = 4;
constexpr int OFF_BAR = 14 * SLOT;
constexpr int OFF_STAT = OFF_BAR + 384;
constexpr int OFF_CH = OFF_STAT + 1024;
constexpr int OFF_TS = OFF_CH + 1536;
constexpr int SMEM_BYTES = OFF_TS + 128;
constexpr int B_FULLX = 0, B_EMPTYX = 8, B_FULLR = 16, B_EMPTYR = 20, B_FULLP = 24, B_EMPTYP = 31, B_STFULL = 38  ,
              B_STFREE = 40  , B_RDY = 43  , B_FULLS = 46  ;
constexpr int NB_STATS = 1, NB_H0 = 2  , NB_END = 6;
constexpr int SPIN_LIMIT = 1 << 18;
#define TH1 2
#define TH2 2
constexpr int ACT_RB = 40 * SLOT;

struct Params {
  CUtensorMap mW[6];
  CUtensorMap mX, mXN, mC[2], mWd;
  const __nv_bfloat16 *x, *lre, *lim, *bre, *bim, *cre, *cim, *logdt, *dskip, *wg, *wu, *wd;
  float* out;
  uint32_t zero;
  int sp[22];
  int fa[22], fb[22];
  int4 at[4][22];
};

__device__ __align__(1024) unsigned char g_act[16 * ACT_RB];
__device__ __align__(1024) unsigned char g_X[16 * 4 * 2 * SLOT];
__device__ __align__(1024) __nv_bfloat16 g_xn[2048 * D_];
__device__ __align__(128) uint32_t g_E[16 * 512 * 2];
__device__ __align__(128) uint32_t g_stat[2048 * 2];
__device__ __align__(128) uint32_t g_CS[1024];
__device__ __align__(128) uint32_t g_cnt[16 * 32];
__device__ __align__(128) uint32_t g_epoch[128 * 8];
#define TS1(i)
#define TSW(i)
#define TSD(i)
#define TSD1(i)

__device__ __forceinline__ uint32_t smem_u32(const void* p) { return (uint32_t)__cvta_generic_to_shared(p); }
__device__ __forceinline__ void mbar_init(uint32_t bar, uint32_t cnt) {
  asm volatile("mbarrier.init.shared::cta.b64 [%0], %1;" ::"r"(bar), "r"(cnt) : "memory");
}
__device__ __forceinline__ void mbar_expect(uint32_t bar, uint32_t bytes) {
  asm volatile("mbarrier.arrive.expect_tx.shared::cta.b64 _, [%0], %1;" ::"r"(bar), "r"(bytes) : "memory");
}
__device__ __forceinline__ void mbar_arrive(uint32_t bar) {
  asm volatile("mbarrier.arrive.shared::cta.b64 _, [%0];" ::"r"(bar) : "memory");
}
__device__ __forceinline__ void mbar_arrive_cta(uint32_t bar, uint32_t cta, uint32_t cnt) {
  asm volatile(
      "{\n.reg .b32 ra;\nmapa.shared::cluster.u32 ra, %0, %1;\n"
      "mbarrier.arrive.shared::cluster.b64 _, [ra], %2;\n}" ::"r"(bar), "r"(cta), "r"(cnt) : "memory");
}
__device__ __forceinline__ void mbar_arrive_addr(uint32_t cluster_addr) {
  asm volatile("mbarrier.arrive.shared::cluster.b64 _, [%0];" ::"r"(cluster_addr) : "memory");
}
__device__ __forceinline__ uint32_t mapa(uint32_t a, uint32_t cta) {
  uint32_t r; asm("mapa.shared::cluster.u32 %0, %1, %2;" : "=r"(r) : "r"(a), "r"(cta)); return r;
}
__device__ __forceinline__ void mbar_wait(uint32_t bar, uint32_t parity) {
  asm volatile(
      "{\n.reg .pred p;\n.reg .s32 n;\n"
      "mbarrier.try_wait.parity.shared::cta.b64 p, [%0], %1;\n@p bra DONE;\nmov.s32 n, %2;\n"
      "LOOP:\nmbarrier.try_wait.parity.shared::cta.b64 p, [%0], %1;\n@p bra DONE;\n"
      "sub.s32 n, n, 1;\nsetp.gt.s32 p, n, 0;\n@p bra LOOP;\nDONE:\n}"
      ::"r"(bar), "r"(parity), "n"(SPIN_LIMIT) : "memory");
}
__device__ __forceinline__ bool mbar_try(uint32_t bar, uint32_t parity) {
  uint32_t ok;
  asm volatile(
      "{\n.reg .pred p;\nmbarrier.try_wait.parity.shared::cta.b64 p, [%1], %2;\nselp.u32 %0, 1, 0, p;\n}"
      : "=r"(ok) : "r"(bar), "r"(parity) : "memory");
  return ok;
}
__device__ __forceinline__ void mbar_wait1(uint32_t bar, uint32_t parity) {
  if (!mbar_try(bar, parity)) {
    int it = SPIN_LIMIT;
    while (!mbar_try(bar, parity) && --it > 0) {}
  }
}
__device__ __forceinline__ void tma3d(uint32_t dst, const CUtensorMap* map, int c1, int c2, uint32_t bar) {
  asm volatile(
      "cp.async.bulk.tensor.3d.shared::cluster.global.mbarrier::complete_tx::bytes [%0], [%1, {%5, %3, %4}], [%2];"
      ::"r"(dst), "l"(map), "r"(bar), "r"(c1), "r"(c2), "r"(0) : "memory");
}
__device__ __forceinline__ void tma5d(uint32_t dst, const CUtensorMap* map, int c0, int c4, uint32_t bar) {
  asm volatile(
      "cp.async.bulk.tensor.5d.shared::cluster.global.mbarrier::complete_tx::bytes [%0], [%1, {%3, %5, %5, %5, %4}], [%2];"
      ::"r"(dst), "l"(map), "r"(bar), "r"(c0), "r"(c4), "r"(0) : "memory");
}
__device__ __forceinline__ void tma2d(uint32_t dst, const CUtensorMap* map, int c0, int c1, uint32_t bar) {
  asm volatile(
      "cp.async.bulk.tensor.2d.shared::cluster.global.mbarrier::complete_tx::bytes [%0], [%1, {%3, %4}], [%2];"
      ::"r"(dst), "l"(map), "r"(bar), "r"(c0), "r"(c1) : "memory");
}
__device__ __forceinline__ void tma5d_mc(uint32_t dst, const CUtensorMap* map, int c0, int c3, int c4, uint32_t bar) {
  asm volatile(
      "cp.async.bulk.tensor.5d.shared::cluster.global.mbarrier::complete_tx::bytes.multicast::cluster "
      "[%0], [%1, {%3, %6, %6, %4, %5}], [%2], %7;"
      ::"r"(dst), "l"(map), "r"(bar), "r"(c0), "r"(c3), "r"(c4), "r"(0), "h"((uint16_t)3) : "memory");
}
__device__ __forceinline__ void bulk_ld_mc(uint32_t dst, const void* src, uint32_t bytes, uint32_t bar) {
  asm volatile(
      "cp.async.bulk.shared::cluster.global.mbarrier::complete_tx::bytes.multicast::cluster [%0], [%1], %2, [%3], %4;"
      ::"r"(dst), "l"(src), "r"(bytes), "r"(bar), "h"((uint16_t)3) : "memory");
}
__device__ __forceinline__ void bulk_st(void* dst, uint32_t src, uint32_t bytes) {
  asm volatile("cp.async.bulk.global.shared::cta.bulk_group [%0], [%1], %2;" ::"l"(dst), "r"(src), "r"(bytes) : "memory");
}
__device__ __forceinline__ void prefetch_l2(const void* p, uint32_t bytes) {
  asm volatile("cp.async.bulk.prefetch.L2.global [%0], %1;" ::"l"(p), "r"(bytes) : "memory");
}
__device__ __forceinline__ void prefetch_map(const CUtensorMap* m) {
  asm volatile("prefetch.tensormap [%0];" ::"l"(m) : "memory");
}
__device__ __forceinline__ void nb_sync(int id, int n) { asm volatile("bar.sync %0, %1;" ::"r"(id), "r"(n) : "memory"); }
__device__ __forceinline__ void nb_arrive(int id, int n) { asm volatile("bar.arrive %0, %1;" ::"r"(id), "r"(n) : "memory"); }
__device__ __forceinline__ void wg_fence() { asm volatile("wgmma.fence.sync.aligned;" ::: "memory"); }
__device__ __forceinline__ void wg_commit() { asm volatile("wgmma.commit_group.sync.aligned;" ::: "memory"); }
template <int N> __device__ __forceinline__ void wg_wait() { asm volatile("wgmma.wait_group.sync.aligned %0;" ::"n"(N) : "memory"); }
template <int LO, int HI> __device__ __forceinline__ void pin(float (&d)[64]) {
#pragma unroll
  for (int i = LO; i < HI; i++) asm volatile("" : "+f"(d[i])::"memory");
}
__device__ __forceinline__ void fence_async_smem() { asm volatile("fence.proxy.async.shared::cta;" ::: "memory"); }
__device__ __forceinline__ void fence_async_global() { asm volatile("fence.proxy.async.global;" ::: "memory"); }
__device__ __forceinline__ bool elect() {
  uint32_t p;
  asm volatile("{\n.reg .pred P;\nelect.sync _|P, 0xffffffff;\nselp.u32 %0, 1, 0, P;\n}" : "=r"(p));
  return p;
}
__device__ __forceinline__ float tanh_approx(float x) { float r; asm("tanh.approx.f32 %0, %1;" : "=f"(r) : "f"(x)); return r; }
__device__ __forceinline__ uint32_t ld_relaxed(const uint32_t* p) {
  uint32_t v; asm volatile("ld.relaxed.gpu.global.u32 %0, [%1];" : "=r"(v) : "l"(p) : "memory"); return v;
}
__device__ __forceinline__ uint32_t ld_acquire(const uint32_t* p) {
  uint32_t v; asm volatile("ld.acquire.gpu.global.u32 %0, [%1];" : "=r"(v) : "l"(p) : "memory"); return v;
}
__device__ __forceinline__ uint2 ld_relaxed2(const uint32_t* p) {
  uint2 v; asm volatile("ld.relaxed.gpu.global.v2.u32 {%0, %1}, [%2];" : "=r"(v.x), "=r"(v.y) : "l"(p) : "memory"); return v;
}
__device__ __forceinline__ void st_relaxed2(uint32_t* p, uint32_t a, uint32_t b) {
  asm volatile("st.relaxed.gpu.global.v2.u32 [%0], {%1, %2};" ::"l"(p), "r"(a), "r"(b) : "memory");
}
__device__ __forceinline__ void st_weak4(void* p, uint32_t a, uint32_t b, uint32_t c, uint32_t d) {
  asm volatile("st.global.v4.u32 [%0], {%1, %2, %3, %4};" ::"l"(p), "r"(a), "r"(b), "r"(c), "r"(d) : "memory");
}
__device__ __forceinline__ uint4 ld_b128(const void* p) {
  uint4 v;
  asm volatile("{\n.reg .b128 t;\n.reg .b64 lo, hi;\nld.relaxed.gpu.global.b128 t, [%4];\nmov.b128 {lo, hi}, t;\n"
               "mov.b64 {%0, %1}, lo;\nmov.b64 {%2, %3}, hi;\n}" : "=r"(v.x), "=r"(v.y), "=r"(v.z), "=r"(v.w) : "l"(p) : "memory");
  return v;
}
__device__ __forceinline__ uint4 ldg_nc4(const void* p) {
  uint4 v; asm volatile("ld.global.nc.v4.u32 {%0, %1, %2, %3}, [%4];" : "=r"(v.x), "=r"(v.y), "=r"(v.z), "=r"(v.w) : "l"(p)); return v;
}
__device__ __forceinline__ uint32_t ldg_u16(const void* p) {
  uint32_t v; asm volatile("ld.global.nc.u16 %0, [%1];" : "=r"(v) : "l"(p)); return v;
}
__device__ __forceinline__ uint32_t ldg_u32(const void* p) {
  uint32_t v; asm volatile("ld.global.nc.u32 %0, [%1];" : "=r"(v) : "l"(p)); return v;
}
__device__ __forceinline__ uint32_t pack_bf16(float lo, float hi) {
  uint32_t r; asm("cvt.rn.bf16x2.f32 %0, %1, %2;" : "=r"(r) : "f"(hi), "f"(lo)); return r;
}
__device__ __forceinline__ float bf_lo(uint32_t v) { return __uint_as_float(v << 16); }
__device__ __forceinline__ float bf_hi(uint32_t v) { return __uint_as_float(v & 0xffff0000u); }
__device__ __forceinline__ uint32_t tagf(float v, uint32_t tag) { return (__float_as_uint(v) & ~1u) | tag; }
__device__ __forceinline__ void stsm4(uint32_t a, uint32_t r0, uint32_t r1, uint32_t r2, uint32_t r3) {
  asm volatile("stmatrix.sync.aligned.m8n8.x4.shared.b16 [%0], {%1, %2, %3, %4};" ::"r"(a), "r"(r0), "r"(r1), "r"(r2), "r"(r3) : "memory");
}
__device__ __forceinline__ void stsm4t(uint32_t a, uint32_t r0, uint32_t r1, uint32_t r2, uint32_t r3) {
  asm volatile("stmatrix.sync.aligned.m8n8.x4.trans.shared.b16 [%0], {%1, %2, %3, %4};" ::"r"(a), "r"(r0), "r"(r1), "r"(r2), "r"(r3) : "memory");
}
__device__ __forceinline__ float4 lds4(uint32_t a) {
  float4 v; asm volatile("ld.shared.v4.f32 {%0, %1, %2, %3}, [%4];" : "=f"(v.x), "=f"(v.y), "=f"(v.z), "=f"(v.w) : "r"(a)); return v;
}
__device__ __forceinline__ uint4 lds4u(uint32_t a) {
  uint4 v; asm volatile("ld.shared.v4.u32 {%0, %1, %2, %3}, [%4];" : "=r"(v.x), "=r"(v.y), "=r"(v.z), "=r"(v.w) : "r"(a)); return v;
}
__device__ __forceinline__ void sts2(uint32_t a, float x, float y) {
  asm volatile("st.shared.v2.f32 [%0], {%1, %2};" ::"r"(a), "f"(x), "f"(y) : "memory");
}
__device__ __forceinline__ float lds1(uint32_t a) {
  float v; asm volatile("ld.shared.f32 %0, [%1];" : "=f"(v) : "r"(a)); return v;
}
__device__ __forceinline__ float2 lds2(uint32_t a) {
  float2 v; asm volatile("ld.shared.v2.f32 {%0, %1}, [%2];" : "=f"(v.x), "=f"(v.y) : "r"(a)); return v;
}
__device__ __forceinline__ uint32_t pack_relu_bf16(float lo, float hi) {
  uint32_t r; asm("cvt.rn.relu.bf16x2.f32 %0, %1, %2;" : "=r"(r) : "f"(hi), "f"(lo)); return r;
}
__device__ __forceinline__ uint32_t mul_bf16x2(uint32_t a, uint32_t b) {
  uint32_t r; asm("mul.rn.bf16x2 %0, %1, %2;" : "=r"(r) : "r"(a), "r"(b)); return r;
}
__device__ __forceinline__ uint32_t fma_bf16x2(uint32_t a, uint32_t b, uint32_t c) {
  uint32_t r; asm("fma.rn.bf16x2 %0, %1, %2, %3;" : "=r"(r) : "r"(a), "r"(b), "r"(c)); return r;
}
constexpr uint64_t D_K128 = (1ull << 16) | (64ull << 32) | (1ull << 62), D_N128 = (512ull << 16) | (64ull << 32) | (1ull << 62);
constexpr uint64_t D_K64 = (1ull << 16) | (32ull << 32) | (2ull << 62), D_N64 = (512ull << 16) | (32ull << 32) | (2ull << 62);
constexpr uint64_t D_WD = (256ull << 16) | (64ull << 32) | (1ull << 62);
__device__ __forceinline__ uint64_t opaque(uint64_t v) { asm volatile("mov.b64 %0, %0;" : "+l"(v)); return v; }

template <int TB>
__device__ __forceinline__ void wgmma_n128(float (&d)[64], uint64_t da, uint64_t db, int scale_d) {
  asm volatile(
      "{\n.reg .pred p;\nsetp.ne.b32 p, %66, 0;\n"
      "wgmma.mma_async.sync.aligned.m64n128k16.f32.bf16.bf16 "
      "{%0, %1, %2, %3, %4, %5, %6, %7, %8, %9, %10, %11, %12, %13, %14, %15, "
      "%16, %17, %18, %19, %20, %21, %22, %23, %24, %25, %26, %27, %28, %29, %30, %31, "
      "%32, %33, %34, %35, %36, %37, %38, %39, %40, %41, %42, %43, %44, %45, %46, %47, "
      "%48, %49, %50, %51, %52, %53, %54, %55, %56, %57, %58, %59, %60, %61, %62, %63}, "
      "%64, %65, p, 1, 1, 0, %67;\n}\n"
      : "+f"(d[0]), "+f"(d[1]), "+f"(d[2]), "+f"(d[3]), "+f"(d[4]), "+f"(d[5]), "+f"(d[6]), "+f"(d[7]),
        "+f"(d[8]), "+f"(d[9]), "+f"(d[10]), "+f"(d[11]), "+f"(d[12]), "+f"(d[13]), "+f"(d[14]), "+f"(d[15]),
        "+f"(d[16]), "+f"(d[17]), "+f"(d[18]), "+f"(d[19]), "+f"(d[20]), "+f"(d[21]), "+f"(d[22]), "+f"(d[23]),
        "+f"(d[24]), "+f"(d[25]), "+f"(d[26]), "+f"(d[27]), "+f"(d[28]), "+f"(d[29]), "+f"(d[30]), "+f"(d[31]),
        "+f"(d[32]), "+f"(d[33]), "+f"(d[34]), "+f"(d[35]), "+f"(d[36]), "+f"(d[37]), "+f"(d[38]), "+f"(d[39]),
        "+f"(d[40]), "+f"(d[41]), "+f"(d[42]), "+f"(d[43]), "+f"(d[44]), "+f"(d[45]), "+f"(d[46]), "+f"(d[47]),
        "+f"(d[48]), "+f"(d[49]), "+f"(d[50]), "+f"(d[51]), "+f"(d[52]), "+f"(d[53]), "+f"(d[54]), "+f"(d[55]),
        "+f"(d[56]), "+f"(d[57]), "+f"(d[58]), "+f"(d[59]), "+f"(d[60]), "+f"(d[61]), "+f"(d[62]), "+f"(d[63])
      : "l"(da), "l"(db), "r"(scale_d), "n"(TB));
}

template <int TB>
__device__ __forceinline__ void wgmma_n64(float (&d)[64], uint64_t da, uint64_t db, int scale_d) {
  asm volatile(
      "{\n.reg .pred p;\nsetp.ne.b32 p, %34, 0;\n"
      "wgmma.mma_async.sync.aligned.m64n64k16.f32.bf16.bf16 "
      "{%0, %1, %2, %3, %4, %5, %6, %7, %8, %9, %10, %11, %12, %13, %14, %15, "
      "%16, %17, %18, %19, %20, %21, %22, %23, %24, %25, %26, %27, %28, %29, %30, %31}, "
      "%32, %33, p, 1, 1, 0, %35;\n}\n"
      : "+f"(d[0]), "+f"(d[1]), "+f"(d[2]), "+f"(d[3]), "+f"(d[4]), "+f"(d[5]), "+f"(d[6]), "+f"(d[7]),
        "+f"(d[8]), "+f"(d[9]), "+f"(d[10]), "+f"(d[11]), "+f"(d[12]), "+f"(d[13]), "+f"(d[14]), "+f"(d[15]),
        "+f"(d[16]), "+f"(d[17]), "+f"(d[18]), "+f"(d[19]), "+f"(d[20]), "+f"(d[21]), "+f"(d[22]), "+f"(d[23]),
        "+f"(d[24]), "+f"(d[25]), "+f"(d[26]), "+f"(d[27]), "+f"(d[28]), "+f"(d[29]), "+f"(d[30]), "+f"(d[31])
      : "l"(da), "l"(db), "r"(scale_d), "n"(TB));
}

struct cplx { float re, im; };
__device__ __forceinline__ cplx cmul(cplx a, cplx b) { return {a.re * b.re - a.im * b.im, a.re * b.im + a.im * b.re}; }
__device__ __forceinline__ cplx cfma(cplx a, cplx b, cplx c) {
  return {fmaf(-a.im, b.im, fmaf(a.re, b.re, c.re)), fmaf(a.im, b.re, fmaf(a.re, b.im, c.im))};
}
__device__ __forceinline__ cplx ldsc(uint32_t a) { const float2 v = lds2(a); return {v.x, v.y}; }
__device__ __forceinline__ void sincos_cw(float x, float& sn, float& cs) {
  const float k = rintf(x * 0.636619772f);
  float r = fmaf(k, -1.57079601e+00f, x);
  r = fmaf(k, -3.13916473e-07f, r);
  r = fmaf(k, -5.39030253e-15f, r);
  const float z = r * r;
  const float sp = fmaf(fmaf(fmaf(-1.95152959e-4f, z, 8.33216087e-3f), z, -1.66666546e-1f) * z, r, r);
  const float cp = fmaf(fmaf(fmaf(fmaf(2.44331571e-5f, z, -1.38873162e-3f), z, 4.16666457e-2f), z, -0.5f), z, 1.f);
  const int n = (int)k;
  const float a = (n & 1) ? cp : sp, b = (n & 1) ? sp : cp;
  sn = (n & 2) ? -a : a;
  cs = ((n + 1) & 2) ? -b : b;
}

__host__ __device__ __forceinline__ int slice_start(int j) { return j < 4 ? 192 * j : 736 + 160 * (j - 4); }

__device__ __forceinline__ int xslot(int kc) { return kc < 4 ? kc : 2 * kc - 2; }

__device__ __forceinline__ uint32_t cs_off(int w, int v) {
  return (SL_ST + 1) * SLOT + (v >> 3) * 128 + (((2 * w + ((v >> 2) & 1)) ^ (v >> 3)) << 4) + (v & 3) * 4;
}

struct Ctx {
  uint32_t sb;
  int rb, q, hf, j, nt;
  bool heavy;
};
__device__ __forceinline__ uint32_t BAR(const Ctx& c, int i) { return c.sb + OFF_BAR + 8 * i; }

template <int MODE>
__device__ __forceinline__ void p1_job(const Ctx& c, int job, uint32_t flip, uint32_t rel, uint32_t rt, float (&a0)[64], float (&a1)[64]) {
  const uint32_t sb4 = (c.sb & 0x3FFFF) >> 4;
  constexpr int KW = MODE == 0 ? 2 : 128;
  uint64_t dx = opaque(D_K128 | sb4);
  const uint64_t dw0 = opaque((MODE == 0 ? D_K128 : D_N128) | sb4);
#pragma unroll 1
  for (int hh = 0; hh < 2; hh++) {
    const uint32_t xb = BAR(c, B_FULLX) + 32 * hh, xs = 1024 << hh;
#pragma unroll
    for (int i = 0; i < 4; i++) {
      uint64_t dw;
      if (MODE == 0) {
        mbar_wait(xb + 8 * i, 0);
        mbar_wait(BAR(c, 0) + 8 * (hh ? (i < 2 ? B_FULLS + i : B_FULLR + i) : B_FULLR + (i ^ 2)), i < 2 ? 0 : hh);
        dw = dw0 + 1024 * (hh ? (i < 2 ? SL_ST + i : 7 + 2 * i) : 7 + 2 * (i ^ 2));
      } else {
        if (job == 1) mbar_wait(xb + 8 * i, 1);
        mbar_wait(BAR(c, B_FULLR + i), hh ^ flip ^ (i < 2));
        dw = dw0 + 1024 * (7 + 2 * i);
      }
      if (i == 0 && hh == 0) { if (MODE == 0) TSD(104); else if (job == 1) TSD(112); }
      const uint64_t dx2 = opaque(dx + (MODE == 0 ? 0 : 512)), dw2 = opaque(dw + (MODE == 0 ? 512 : 0));
      wg_fence();
#pragma unroll
      for (int k = 0; k < 4; k++) {
        const int sc = (i | k) != 0 || hh != 0;
        if (MODE == 0) wgmma_n128<0>(a0, dw + KW * k, dx + 2 * k, sc);
        else wgmma_n128<1>(a0, dx + 2 * k, dw + KW * k, sc);
      }
#pragma unroll
      for (int k = 0; k < 4; k++) {
        const int sc = (i | k) != 0 || hh != 0;
        if (MODE == 0) wgmma_n128<0>(a1, dw2 + KW * k, dx2 + 2 * k, sc);
        else wgmma_n128<1>(a1, dx2 + 2 * k, dw2 + KW * k, sc);
      }
      wg_commit();
      if (i == 3 && hh) nb_arrive(NB_H0 + job, 256);
      dx += i < 3 ? xs : 3072;
      wg_wait<1>();
      const uint32_t n = rt & 15;
      rt >>= 4;
      if (n != 15) mbar_arrive_addr(rel + 8 * n);
    }
  }
}

__device__ __forceinline__ void p1_job32(const Ctx& c, uint32_t rel, uint32_t rt, float (&a0)[64], float (&a1)[64]) {
  const uint32_t sb4 = (c.sb & 0x3FFFF) >> 4;
  uint64_t dx = opaque(D_K128 | sb4), dw = opaque(D_N64 | (sb4 + 7 * 1024));
#pragma unroll 1
  for (int i = 0; i < 4; i++) {
    mbar_wait(BAR(c, B_FULLR) + 8 * i, i < 2);
    wg_fence();
#pragma unroll 1
    for (int u = 0; u < 2; u++) {
#pragma unroll
      for (int k = 0; k < 4; k++) wgmma_n64<1>(a0, dx + 2 * k, dw + 64 * k, (i | u | k) != 0);
#pragma unroll
      for (int k = 0; k < 4; k++) wgmma_n64<1>(a1, dx + 512 + 2 * k, dw + 64 * k, (i | u | k) != 0);
      dx += i < 2 ? (i + u == 2 ? 3072 : 1024) : 2048;
      dw += u ? 2048 - 256 : 256;
    }
    wg_commit();
    if (i == 3) nb_arrive(NB_H0 + 2, 256);
    wg_wait<1>();
    const uint32_t n = rt & 15;
    rt >>= 4;
    if (n != 15) mbar_arrive_addr(rel + 8 * n);
  }
}

template <bool ISY>
__device__ __forceinline__ void phase2(const Params& p, const Ctx& c, int w, float (&acc)[64]) {
  constexpr int TB = ISY ? 0 : 1;
  constexpr int NS = ISY ? 16 : 22;
  constexpr int L = 4;
  constexpr int HB = ISY ? 512 : 256;
#define KBO(k) (ISY ? 2 * (k) : ((k) & 1) * 128 + ((k) >> 1) * 512)
  constexpr int SEND = ISY ? 32 : 0, OWN = ISY ? 0 : 32;
  const int lane = threadIdx.x & 31, warp = (threadIdx.x >> 5) & 3, tid = w * 128 + (threadIdx.x & 127);
  const uint32_t sb4 = (c.sb & 0x3FFFF) >> 4;
  const uint64_t da0 = opaque(D_K128 | (sb4 + w * 512)), db0 = opaque((ISY ? D_K128 : D_WD) | (sb4 + 1024));
  const uint32_t rel = mapa(BAR(c, B_EMPTYP), lane & 1);
  const int q = lane & 3;
  const int n0 = 64 * w + 16 * warp + (lane >> 2);
  const int col0 = 128 * c.nt + (ISY ? 0 : 64) + 2 * q;
  const int t0 = c.rb * 128 + 32 * ((n0 >> 1) & 3) + 2 * (n0 >> 3) + (n0 & 1);
  uint32_t xr[16], dk[8];
  uint32_t tag;
  auto load_operands = [&]() {
    tag = ld_relaxed(g_epoch + blockIdx.x * 8);
#pragma unroll
    for (int j = 0; j < 8; j++) {
      xr[2 * j] = ldg_u32(p.x + (size_t)t0 * D_ + col0 + 8 * j);
      xr[2 * j + 1] = ldg_u32(p.x + (size_t)(t0 + 2) * D_ + col0 + 8 * j);
      dk[j] = ldg_u32(p.dskip + col0 + 8 * j);
    }
  };
  if (w == 1) { load_operands(); nb_sync(NB_H0 + 3, 256); }
#pragma unroll
  for (int i = 0; i < 3; i++) {
    const int st = i + (i == 2);
    mbar_wait(BAR(c, B_FULLP + st), 0);
    if (w == 1 && i == 0) TSD(64);
    wg_fence();
#pragma unroll
    for (int k = 0; k < 4; k++) wgmma_n128<TB>(acc, da0 + st * 2048 + 2 * k, db0 + st * 2048 + KBO(k), (i | k) != 0);
    wg_commit();
    if (i > 0) {
      wg_wait<1>();
      if (lane < 2) mbar_arrive_addr(rel + 8 * (i - 1));
    }
  }
  {
    uint32_t s8 = 32, ph = 0, pa = rel + 24;
    int nrel = lane < 2 ? NS - 9 : 0;
#pragma unroll 1
    for (int i = 3; i < (ISY ? NS - L : 15); i++) {
      mbar_wait(BAR(c, B_FULLP) + s8, ph);
      if (w == 1 && i == 6) TSD(70);
      const uint64_t da = da0 + s8 * 256, db = db0 + s8 * 256;
      wg_fence();
#pragma unroll
      for (int k = 0; k < 4; k++) wgmma_n128<TB>(acc, da + 2 * k, db + KBO(k), 1);
      wg_commit();
      wg_wait<1>();
      if (--nrel >= 0) mbar_arrive_addr(pa);
      pa = rel + s8;
      s8 += 8;
      if (s8 == 56) { s8 = 0; ph ^= 1; }
    }
  }
  if (!ISY) {
    const uint64_t dh = opaque(D_K64 | (sb4 + w * 256));
#pragma unroll
    for (int st = 2; st < 5; st++) {
      mbar_wait(BAR(c, B_FULLP + st), 0);
      wg_fence();
#pragma unroll
      for (int k = 0; k < (st < 4 ? 4 : 2); k++)
        wgmma_n128<TB>(acc, dh + st * 2048 + (k >> 1) * 512 + (k & 1) * 2, db0 + st * 2048 + KBO(k), 1);
      wg_commit();
      if (st == 2) {
        wg_wait<1>();
        if (lane < 2) mbar_arrive_addr(rel + 8);
      }
    }
  }
  if (w == 0) load_operands();
  unsigned char* xb = g_X + (size_t)((c.rb * 4 + c.nt) * 2) * SLOT + tid * 16;
  wg_wait<0>();
  pin<0, 64>(acc);
  float hs[64], ho[64];
#pragma unroll
  for (int i = 0; i < 32; i++) {
    asm volatile("mov.b32 %0, %1;" : "=f"(hs[i]) : "f"(acc[SEND + i]));
    asm volatile("mov.b32 %0, %1;" : "=f"(ho[i]) : "f"(acc[OWN + i]));
  }
  if (w) TSW(41); else TSW(40);
  constexpr int V0 = NS - L + 1;
  int s = V0 % 7, ph = (V0 / 7) & 1;
#pragma unroll 1
  for (int i = 0; i < L; i++) {
    mbar_wait(BAR(c, B_FULLP) + 8 * s, ph);
    wg_fence();
#pragma unroll
    for (int k = 0; k < 4; k++) wgmma_n64<TB>(hs, da0 + s * 2048 + 2 * k, db0 + s * 2048 + (SEND ? HB : 0) + KBO(k), 1);
    if (++s == 7) { s = 0; ph ^= 1; }
  }
  wg_commit();
  wg_fence();
#pragma unroll
  for (int k = 0; k < 4; k++)
    wgmma_n64<TB>(ho, da0 + V0 % 7 * 2048 + 2 * k, db0 + V0 % 7 * 2048 + (OWN ? HB : 0) + KBO(k), 1);
  wg_commit();
  wg_wait<1>();
  pin<0, 32>(hs);
  tag = (tag + 1) & 1;
  if (w) TSW(43); else TSW(42);
#pragma unroll
  for (int k = 0; k < 4; k++) {
    const uint32_t w0 = (pack_bf16(hs[8 * k], hs[8 * k + 1]) & ~1u) | tag;
    st_weak4(xb + (ISY ? 0 : SLOT) + k * 4096, w0, pack_bf16(hs[8 * k + 2], hs[8 * k + 3]),
             pack_bf16(hs[8 * k + 4], hs[8 * k + 5]), pack_bf16(hs[8 * k + 6], hs[8 * k + 7]));
  }
  s = (V0 + 1) % 7;
#pragma unroll 1
  for (int i = 1; i < L; i++) {
    wg_fence();
#pragma unroll
    for (int k = 0; k < 4; k++) wgmma_n64<TB>(ho, da0 + s * 2048 + 2 * k, db0 + s * 2048 + (OWN ? HB : 0) + KBO(k), 1);
    if (++s == 7) s = 0;
  }
  wg_commit();
  uint4 rx[4];
  const float2 st0 = lds2(c.sb + OFF_STAT + n0 * 8), st1 = lds2(c.sb + OFF_STAT + (n0 + 8) * 8);
  const float nm0 = -st0.x * st0.y, nm1 = -st1.x * st1.y;
  {
    int it = SPIN_LIMIT;
    do {
#pragma unroll
      for (int k = 0; k < 4; k++) rx[k] = ld_b128(xb + (ISY ? SLOT : 0) + k * 4096);
    } while ((((rx[0].x ^ tag) | (rx[1].x ^ tag) | (rx[2].x ^ tag) | (rx[3].x ^ tag)) & 1u) && --it > 0);
  }
  if (w) TSW(45); else TSW(44);
  wg_wait<0>();
  pin<0, 32>(ho);
  float* o0 = p.out + (size_t)t0 * D_ + col0;
#pragma unroll
  for (int j = 0; j < 8; j++) {
    const uint32_t r0 = (j & 1) ? rx[j >> 1].z : rx[j >> 1].x, r1 = (j & 1) ? rx[j >> 1].w : rx[j >> 1].y;
    float v[4];
#pragma unroll
    for (int e = 0; e < 4; e++) {
      const uint32_t rr = e < 2 ? r0 : r1, xx = xr[2 * j + (e >> 1)];
      const float other = (e & 1) ? bf_hi(rr) : bf_lo(rr);
      const float xv = (e & 1) ? bf_hi(xx) : bf_lo(xx);
      const float dsk = (e & 1) ? bf_hi(dk[j]) : bf_lo(dk[j]);
      const float y = ISY ? ho[4 * j + e] : other;
      const float dh = 0.5f * (ISY ? other : ho[4 * j + e]);
      const float sv = fmaf(fmaf(xv, e < 2 ? st0.y : st1.y, e < 2 ? nm0 : nm1), dsk, y);
      const float g = fmaf(dh, tanh_approx(dh), dh);
      v[e] = fmaf(sv, g, xv);
    }
    *(float2*)(o0 + 8 * j) = make_float2(v[0], v[1]);
    *(float2*)(o0 + 2 * D_ + 8 * j) = make_float2(v[2], v[3]);
  }
  if (w) TSW(49); else TSW(48);
}

__device__ __forceinline__ void publish(const void* last, uint32_t* cnt) {
  fence_async_global();
  const uint32_t v = ld_relaxed((const uint32_t*)last);
  asm volatile("{\n.reg .pred p;\nsetp.ne.b32 p, %1, 0x7fc17fc1;\n@p red.relaxed.gpu.global.add.u32 [%0], 1;\n@!p red.relaxed.gpu.global.add.u32 [%0], 1;\n}" ::"l"(cnt), "r"(v) : "memory");
}
__device__ __forceinline__ void poll_count(const uint32_t* p, uint32_t target) {
  int it = SPIN_LIMIT;
  while (ld_acquire(p) != target && --it > 0) {}
  fence_async_global();
}

__global__ void __cluster_dims__(2, 1, 1) __launch_bounds__(512, 1) fused_kernel(const __grid_constant__ Params p) {
  extern __shared__ __align__(1024) unsigned char smem[];
  Ctx c;
  c.sb = smem_u32(smem);
  {
    const int cl = blockIdx.x >> 1;
    int grp, idx;
    if (cl < 4) { grp = 0; idx = 4 + cl; }
    else if (cl < 36) { grp = (cl - 4) & 7; idx = (cl - 4) >> 3; }
    else { grp = 1 + (cl - 36) % 7; idx = 4 + (cl - 36) / 7; }
    c.q = grp >> 1;
    c.rb = (grp & 1) * 8 + idx;
    c.hf = blockIdx.x & 1;
    c.j = 2 * c.q + c.hf;
    c.nt = 2 * (c.q & 1) + c.hf;
    c.heavy = c.j < 3;
  }
  const int warp_id = __shfl_sync(0xffffffffu, threadIdx.x >> 5, 0), lane = threadIdx.x & 31;
  uint32_t ep0 = 0, raw[3];
  if (warp_id >= 4) ep0 = ld_relaxed(g_epoch + blockIdx.x * 8);
  uint4 b0, b1;
  if (warp_id >= 8) {
    const char* bs = (const char*)((warp_id < 12 ? p.bre : p.bim) + (size_t)(64 * c.j + 4 * c.rb + (warp_id & 3)) * D_) + lane * 16;
    b0 = ldg_nc4(bs); b1 = ldg_nc4(bs + 512);
  }
  if (warp_id >= 14) {
    const int ch = 64 * c.j + threadIdx.x - 448;
    raw[0] = ldg_u16(p.lre + ch); raw[1] = ldg_u16(p.lim + ch); raw[2] = ldg_u16(p.logdt + ch);
  }
  if (warp_id < 2) {
    if (elect()) {
      if (warp_id == 0) {
#pragma unroll
        for (int i = 0; i < 4; i++) { mbar_init(BAR(c, B_FULLR + i), 1); mbar_init(BAR(c, B_EMPTYR + i), 4); }
        mbar_init(BAR(c, B_FULLS), 1); mbar_init(BAR(c, B_FULLS + 1), 1);
      } else {
#pragma unroll
        for (int i = 0; i < 8; i++) mbar_init(BAR(c, B_FULLX + i), 1);
      }
      asm volatile("fence.mbarrier_init.release.cluster;" ::: "memory");
    }
    __syncwarp();
    nb_arrive(0, 512);
    asm volatile("barrier.cluster.arrive.relaxed.aligned;" ::: "memory");
  } else {
    if (warp_id < 4 && elect()) {
      if (warp_id == 2) {
        prefetch_map(&p.mX); prefetch_map(&p.mW[0]); prefetch_map(&p.mW[1]);
#pragma unroll
        for (int i = 0; i < 7; i++) { mbar_init(BAR(c, B_FULLP + i), 2); mbar_init(BAR(c, B_EMPTYP + i), 16); }
        mbar_arrive_cta(BAR(c, B_FULLP + 2), c.hf, 2);
        mbar_arrive_cta(BAR(c, B_EMPTYP + 2), c.hf, 16);
      } else {
#pragma unroll
        for (int i = 0; i < 8; i++) mbar_init(BAR(c, B_EMPTYX + i), 24);
        mbar_init(BAR(c, B_STFULL), 4); mbar_init(BAR(c, B_STFULL + 1), 4);
#pragma unroll
        for (int i = 0; i < 6; i++) mbar_init(BAR(c, B_STFREE + i), 1);
      }
      asm volatile("fence.mbarrier_init.release.cluster;" ::: "memory");
    }
    __syncwarp();
    nb_sync(0, 512);
    asm volatile("barrier.cluster.arrive.relaxed.aligned;" ::: "memory");
  }
  const int f0 = slice_start(c.j);

  if (warp_id < 4) {
    asm volatile("setmaxnreg.dec.sync.aligned.u32 24;");
    if (warp_id == 0) {
      if (elect()) {
#pragma unroll
        for (int i = 0; i < 6; i++) {
          const uint32_t full = BAR(c, i < 4 ? B_FULLR + (i ^ 2) : B_FULLS + i - 4);
          const uint32_t dst = c.sb + (i < 4 ? 7 + 2 * (i ^ 2) : SL_ST + i - 4) * SLOT;
          mbar_expect(full, SLOT);
          tma2d(dst, &p.mW[0], 64 * i, 64 * c.j, full);
          tma2d(dst + 8192, &p.mW[1], 64 * i, 64 * c.j, full);
        }
        TS1(7);
      }
      __syncwarp();
      asm volatile("barrier.cluster.wait.acquire.aligned;" ::: "memory");
      if (elect()) {
#pragma unroll 1
        for (int g = 2; g < 4; g++) {
          const uint32_t full = BAR(c, B_FULLR + g), dst = c.sb + (7 + 2 * g) * SLOT;
          mbar_wait1(full + 32, 0);
          mbar_expect(full, SLOT);
          tma2d(dst, &p.mW[0], 256 + 64 * g, 64 * c.j, full);
          tma2d(dst + 8192, &p.mW[1], 256 + 64 * g, 64 * c.j, full);
        }
#pragma unroll 1
        for (int job = 0; job < 3; job++) {
          if (job == 1 && !c.heavy) {
#pragma unroll 1
            for (int g = 0; g < 4; g++) {
              const uint32_t full = BAR(c, B_FULLR + g), dst = c.sb + (7 + 2 * g) * SLOT;
              mbar_wait1(full + 32, g >> 1);
              mbar_expect(full, SLOT);
              tma2d(dst, &p.mW[4], f0 + 64, 128 * g, full);
              tma2d(dst + 8192, &p.mW[5], f0 + 64, 128 * g, full);
            }
          } else {
            const int fl = job == 2 && !c.heavy, f = f0 + 64 * job - 32 * fl;
#pragma unroll 1
            for (int g = 0; g < 8; g++) {
              const uint32_t full = BAR(c, B_FULLR + (g & 3)), dst = c.sb + (7 + 2 * (g & 3)) * SLOT;
              mbar_wait1(full + 32, ((g >> 2) ^ (g >> 1) ^ fl) & 1);
              mbar_expect(full, SLOT);
              tma2d(dst, &p.mW[2], f, 64 * g, full);
              tma2d(dst + 8192, &p.mW[3], f, 64 * g, full);
            }
          }
        }
        TS1(8);
        if (c.q < 2) {
#pragma unroll 1
          for (int i = 0; i < 16; i++) {
            const int sp = p.sp[i];
            const uint32_t full = BAR(c, B_FULLP) + (sp & 56), dst = c.sb + SLOT + (sp & 56) * 4096;
            mbar_wait1(full + 56, sp & 1);
            mbar_expect(full, SLOT);
            tma2d(dst, &p.mC[i & 1], 64 * (i >> 1), 128 * c.nt, full);
          }
        } else {
#pragma unroll 1
          for (int i = 0; i < 22; i++) {
            const int sp = p.sp[i], fa = p.fa[i], fb = p.fb[i];
            const uint32_t full = BAR(c, B_FULLP) + (sp & 56), dst = c.sb + SLOT + (sp & 56) * 4096;
            mbar_wait1(full + 56, sp & 1);
            mbar_expect(full, SLOT);
            tma3d(dst, &p.mWd, fa, 2 * c.nt, full);
            tma3d(dst + 8192, &p.mWd, fb, 2 * c.nt, full);
          }
        }
        TS1(9);
      }
    } else if (warp_id == 1) {
      if (elect()) {
#pragma unroll
        for (int i = 0; i < 8; i++) {
          mbar_expect(BAR(c, B_FULLX + i), SLOT);
          tma5d(c.sb + (i < 4 ? i : 2 * i - 2) * SLOT, &p.mX, 64 * i, c.rb, BAR(c, B_FULLX + i));
        }
        TS1(2);
      }
      __syncwarp();
      asm volatile("barrier.cluster.wait.acquire.aligned;" ::: "memory");
      if (elect()) {
        const uint32_t epoch = ld_relaxed(g_epoch + blockIdx.x * 8) + 1;
        poll_count(g_cnt + c.rb * 32 + 5, epoch * 64);
        TS1(3);
#pragma unroll 1
        for (int kc = 0; kc < 8; kc++) {
          mbar_wait1(BAR(c, B_EMPTYX + kc), 0);
          if (kc >= 3) mbar_wait1(BAR(c, B_FULLX + kc - 3), 1);
          mbar_expect(BAR(c, B_FULLX + kc), SLOT);
          tma5d_mc(c.sb + xslot(kc) * SLOT + c.hf * 8192, &p.mXN, 64 * kc, 8 * c.hf, c.rb, BAR(c, B_FULLX + kc));
        }
        TS1(4);
        poll_count(g_cnt + c.rb * 32 + (c.q >> 1), epoch * 8);
        const unsigned char* act = g_act + (size_t)c.rb * ACT_RB;
        const int ns = c.q < 2 ? 16 : 22;
        const int4* tab = p.at[(c.q & 2) + c.hf];
#pragma unroll 1
        for (int i = 0; i < ns; i++) {
          const int4 e = tab[i];
          const uint32_t full = BAR(c, B_FULLP) + (e.w & 56);
          if (e.w >> 8) { mbar_wait1(BAR(c, B_RDY) - 8 + (e.w >> 8), 0); fence_async_global(); }
          mbar_wait1(full + 56, e.w & 1);
          TSD1(82 + i);
          mbar_expect(full, SLOT);
          bulk_ld_mc(c.sb + e.y, act + e.x, e.z ? 4096 : 8192, full);
          if (e.z) bulk_ld_mc(c.sb + e.y + 8192, act + e.z, 4096, full);
        }
        TS1(5);
      }
    } else if (warp_id == 2) {
      asm volatile("barrier.cluster.wait.acquire.aligned;" ::: "memory");
      if (elect()) {
        unsigned char* act = g_act + (size_t)c.rb * ACT_RB + (16 + 3 * c.j) * SLOT;
#pragma unroll 1
        for (int k = 0; k < 3; k++) {
          mbar_wait1(BAR(c, B_STFULL + 1), k & 1);
          bulk_st(act + k * SLOT, c.sb + SL_ST * SLOT, (k == 1 && !c.heavy) ? SLOT / 2 : SLOT);
          asm volatile("cp.async.bulk.commit_group;\ncp.async.bulk.wait_group.read 0;" ::: "memory");
          if (k < 2) mbar_arrive(BAR(c, B_STFREE + 1 + k));
          if (k == 2) { mbar_arrive_cta(BAR(c, B_EMPTYP + 2), 0, 4); mbar_arrive_cta(BAR(c, B_EMPTYP + 2), 1, 4); }
          asm volatile("cp.async.bulk.wait_group 0;" ::: "memory");
          publish(act + k * SLOT + 8176, g_cnt + c.rb * 32 + 1 + k + (k == 2 && c.heavy));
          if (k == 0) TS1(11); else if (k == 1) TS1(12); else TS1(13);
        }
      }
    } else {
      asm volatile("barrier.cluster.wait.acquire.aligned;" ::: "memory");
      if (elect()) {
        const uint32_t epoch = ld_relaxed(g_epoch + blockIdx.x * 8) + 1;
#pragma unroll 1
        for (int i = 2; i < 11; i++) prefetch_map(&p.mW[i]);
        mbar_wait1(BAR(c, B_FULLX + 3), 0);
        prefetch_l2(p.wg + (size_t)blockIdx.x * 4 * F_, 4 * F_ * 2);
        prefetch_l2(p.wu + (size_t)blockIdx.x * 4 * F_, 4 * F_ * 2);
        mbar_wait1(BAR(c, B_FULLX + 0), 1);
        prefetch_l2((const char*)p.cre + blockIdx.x * 4096, 4096);
        prefetch_l2((const char*)p.cim + blockIdx.x * 4096, 4096);
        prefetch_l2((const char*)p.wd + blockIdx.x * 11008, 11008);
        unsigned char* act = g_act + (size_t)c.rb * ACT_RB + 2 * c.j * SLOT;
#pragma unroll 1
        for (int k = 0; k < 2; k++) {
          mbar_wait1(BAR(c, B_STFULL), k);
          bulk_st(act + k * 8192, c.sb + (SL_ST + 1) * SLOT, 8192);
          bulk_st(act + SLOT + k * 8192, c.sb + (SL_ST + 1) * SLOT + 8192, 8192);
          asm volatile("cp.async.bulk.commit_group;\ncp.async.bulk.wait_group.read 0;" ::: "memory");
          mbar_arrive(BAR(c, B_STFREE));
        }
        mbar_arrive_cta(BAR(c, B_EMPTYP + 2), 0, 4); mbar_arrive_cta(BAR(c, B_EMPTYP + 2), 1, 4);
        asm volatile("cp.async.bulk.wait_group 0;" ::: "memory");
        publish(act + 2 * SLOT - 16, g_cnt + c.rb * 32);
        TS1(10);
        if (c.q >= 2) {
#pragma unroll 1
          for (int k = 0; k < 3; k++) {
            poll_count(g_cnt + c.rb * 32 + 2 + k, epoch * (k == 0 ? 8 : k == 1 ? 5 : 3));
            mbar_arrive(BAR(c, B_RDY + k));
          }
        }
      }
    }
  } else if (warp_id < 8) {
    asm volatile("setmaxnreg.inc.sync.aligned.u32 168;");
    const int warp = warp_id & 3, q = lane & 3;
    float a0[64], a1[64];
    {
      const int ch0 = 64 * c.j + 16 * warp + (lane >> 2);
      const uint32_t tag = (ep0 + 1) & 1;
      if (q == 3) {
        st_relaxed2(g_E + (c.rb * 512 + ch0) * 2, tag ^ 1, tag ^ 1);
        st_relaxed2(g_E + (c.rb * 512 + ch0 + 8) * 2, tag ^ 1, tag ^ 1);
      }
      TSW(16);
      asm volatile("barrier.cluster.wait.acquire.aligned;" ::: "memory");
      const uint32_t rel = lane == 0 ? mapa(BAR(c, B_EMPTYR), c.hf) : mapa(BAR(c, B_EMPTYX), lane & 1);
      p1_job<0>(c, 0, 0, rel, lane == 0 ? 0x2FF1032Fu : lane < 3 ? 0x6543210Fu : 0xFFFFFFFFu, a0, a1);
      TSW(17);
      wg_wait<0>();
      pin<0, 64>(a0); pin<0, 64>(a1);
      if (lane < 3) mbar_arrive_addr(rel + (lane == 0 ? 24 : 56));
      nb_sync(NB_STATS, 384);
      const uint32_t cht = c.sb + OFF_CH + (16 * warp + (lane >> 2)) * 8;
      const float sre[2] = {lds1(c.sb + cs_off(warp, lane >> 2)), lds1(c.sb + cs_off(warp, 8 + (lane >> 2)))},
                  sim[2] = {lds1(c.sb + cs_off(warp, 16 + (lane >> 2))), lds1(c.sb + cs_off(warp, 24 + (lane >> 2)))};
      const cplx L[2] = {ldsc(cht), ldsc(cht + 64)};
      TSW(18);
      cplx e[2] = {{0.f, 0.f}, {0.f, 0.f}};
      uint32_t zdep = 0;
#pragma unroll
      for (int j = 0; j < 16; j++) {
        if (j % TH1 == 0) zdep = __float_as_uint(e[0].re) & p.zero;
        const float4 st = lds4(c.sb + OFF_STAT + (8 * j + 2 * q) * 8 + zdep);
#pragma unroll
        for (int ee = 0; ee < 2; ee++) {
          const float m = ee ? st.z : st.x, r = ee ? st.w : st.y;
#pragma unroll
          for (int h = 0; h < 2; h++) {
            const int i = 4 * j + 2 * h + ee;
            a0[i] = r * fmaf(-m, sre[h], a0[i]);
            a1[i] = r * fmaf(-m, sim[h], a1[i]);
            e[h] = cfma(L[h], e[h], {a0[i], a1[i]});
          }
        }
      }
      uint32_t t2;
      asm volatile("mov.u32 %0, %%tid.x;" : "=r"(t2));
      const int lane2 = t2 & 31, q2 = t2 & 3, warp2 = (t2 >> 5) & 3, ch2 = 64 * c.j + 16 * warp2 + (lane2 >> 2);
      const uint32_t cht2 = c.sb + OFF_CH + (16 * warp2 + (lane2 >> 2)) * 8;
      const cplx L32[2] = {ldsc(cht2 + 1024), ldsc(cht2 + 1024 + 64)};
#pragma unroll
      for (int h = 0; h < 2; h++) {
        cplx t = {__shfl_up_sync(0xffffffffu, e[h].re, 1, 4), __shfl_up_sync(0xffffffffu, e[h].im, 1, 4)};
        if (q2 >= 1) e[h] = cfma(L32[h], t, e[h]);
        t = {__shfl_up_sync(0xffffffffu, e[h].re, 2, 4), __shfl_up_sync(0xffffffffu, e[h].im, 2, 4)};
        if (q2 >= 2) e[h] = cfma(cmul(L32[h], L32[h]), t, e[h]);
        if (q2 == 3) st_relaxed2(g_E + (c.rb * 512 + ch2 + 8 * h) * 2, tagf(e[h].re, tag), tagf(e[h].im, tag));
        e[h] = {__shfl_up_sync(0xffffffffu, e[h].re, 1, 4), __shfl_up_sync(0xffffffffu, e[h].im, 1, 4)};
        if (q2 == 0) e[h] = {0.f, 0.f};
      }
      TSW(19);
      {
        const uint32_t* eb = g_E + ((c.rb - 1 - q2) * 512 + ch2) * 2;
        uint2 ev[2][4];
        int it = SPIN_LIMIT;
        uint32_t bad;
        do {
          bad = 0;
#pragma unroll
          for (int i = 0; i < 4; i++)
#pragma unroll
            for (int h = 0; h < 2; h++) {
              ev[h][i] = make_uint2(tag, tag);
              if (q2 + 4 * i < c.rb) ev[h][i] = ld_relaxed2(eb - i * 4096 + 16 * h);
              bad |= (ev[h][i].x ^ tag) | (ev[h][i].y ^ tag);
            }
        } while ((bad & 1u) && --it > 0);
        __syncwarp();
#pragma unroll
        for (int h = 0; h < 2; h++) {
          const cplx l64 = cmul(L32[h], L32[h]), l128 = cmul(l64, l64), l256 = cmul(l128, l128), l512 = cmul(l256, l256);
          cplx pt = {__uint_as_float(ev[h][3].x), __uint_as_float(ev[h][3].y)};
#pragma unroll
          for (int i = 2; i >= 0; i--) pt = cfma(l512, pt, {__uint_as_float(ev[h][i].x), __uint_as_float(ev[h][i].y)});
          if (q2 & 1) pt = cmul(pt, l128);
          if (q2 & 2) pt = cmul(pt, l256);
          pt.re += __shfl_xor_sync(0xffffffffu, pt.re, 1); pt.im += __shfl_xor_sync(0xffffffffu, pt.im, 1);
          pt.re += __shfl_xor_sync(0xffffffffu, pt.re, 2); pt.im += __shfl_xor_sync(0xffffffffu, pt.im, 2);
          if (q2 & 1) pt = cmul(pt, L32[h]);
          if (q2 & 2) pt = cmul(pt, l64);
          e[h].re += pt.re; e[h].im += pt.im;
        }
      }
      TSW(20);
      {
        uint32_t kr[2], ki[2], nkr[2], nki[2];
#pragma unroll
        for (int h = 0; h < 2; h++) {
          const cplx k2 = ldsc(cht2 + 512 + 64 * h);
          kr[h] = pack_bf16(k2.re, k2.re); ki[h] = pack_bf16(k2.im, k2.im);
          nkr[h] = kr[h] ^ 0x80008000u; nki[h] = ki[h] ^ 0x80008000u;
        }
        const int i8 = lane2 & 7, mi = lane2 >> 3;
        const uint32_t base = c.sb + (SL_ST + 1) * SLOT + (8 * (mi >> 1) + i8) * 128 + (((2 * warp2 + (mi & 1)) ^ i8) << 4);
        uint32_t pr[32], pi[32];
        cplx Lj[2];
#pragma unroll
        for (int j = 0; j < 16; j++) {
          if (j % TH2 == 0) {
            const uint32_t dep = cht2 + (__float_as_uint(e[0].re) & p.zero);
            Lj[0] = ldsc(dep); Lj[1] = ldsc(dep + 64);
          }
#pragma unroll
          for (int h = 0; h < 2; h++) {
            const int i = 4 * j + 2 * h;
            const cplx g0 = cfma(Lj[h], e[h], {a0[i], a1[i]});
            e[h] = cfma(Lj[h], g0, {a0[i + 1], a1[i + 1]});
            const uint32_t gr = pack_bf16(g0.re, e[h].re), gi = pack_bf16(g0.im, e[h].im);
            pr[2 * j + h] = fma_bf16x2(nki[h], gi, mul_bf16x2(kr[h], gr));
            pi[2 * j + h] = fma_bf16x2(nki[h], gr, mul_bf16x2(nkr[h], gi));
          }
          if ((j & 7) == 7) {
            if (j == 15) mbar_wait(BAR(c, B_STFREE), 0);
#pragma unroll
            for (int k = 0; k < 4; k++) {
              const int o = 2 * (j - 7) + 4 * k;
              stsm4t(base + k * 2048, pr[o], pr[o + 1], pr[o + 2], pr[o + 3]);
              stsm4t(base + 8192 + k * 2048, pi[o], pi[o + 1], pi[o + 2], pi[o + 3]);
            }
            fence_async_smem();
            __syncwarp();
            if (lane2 == 0) mbar_arrive(BAR(c, B_STFULL));
          }
        }
      }
      TSW(21);
    }
  } else {
    asm volatile("setmaxnreg.inc.sync.aligned.u32 160;");
    const int w = (warp_id >> 2) - 2, warp = warp_id & 3;
    float a0[64], a1[64];
    asm volatile("barrier.cluster.wait.acquire.aligned;" ::: "memory");
    {
      const uint32_t tag = (ep0 + 1) & 1;
      const int wi = warp_id - 8, hb = lane >> 4, pc = lane & 7, ck = (lane >> 3) & 1;
      const int n = 64 * (c.j & 1) + 8 * wi + 2 * (c.j >> 1) + hb, t = c.rb * 128 + 16 * c.j + 2 * wi + hb;
      const uint32_t src = c.sb + n * 128 + ((pc ^ (n & 7)) << 4);
      const int ch = 64 * c.j + 4 * c.rb + (wi & 3);
      if (warp_id >= 14) {
        const float lr = bf_lo(raw[0]), li = bf_lo(raw[1]);
        const float dt = __bfloat162float(__float2bfloat16(expf(bf_lo(raw[2]))));
        const float ea = expf(dt * lr);
        float sn, cs;
        sincos_cw(dt * li, sn, cs);
        cplx t = {ea * cs, ea * sn};
        const float inv = __fdividef(2.f, lr * lr + li * li), nr = t.re - 1.f;
        const uint32_t a = c.sb + OFF_CH + (threadIdx.x - 448) * 8;
        sts2(a, t.re, t.im);
        sts2(a + 512, (nr * lr + t.im * li) * inv, (t.im * lr - nr * li) * inv);
#pragma unroll 1
        for (int i = 0; i < 5; i++) t = cmul(t, t);
        sts2(a + 1024, t.re, t.im);
      }
      float f[32];
      float s0 = 0.f, s1 = 0.f, q0 = 0.f, q1 = 0.f;
#pragma unroll
      for (int it = 0; it < 4; it++) {
        if (it == 0) {
          float bsum = (bf_lo(b0.x) + bf_hi(b0.x) + bf_lo(b0.y) + bf_hi(b0.y)) + (bf_lo(b0.z) + bf_hi(b0.z) + bf_lo(b0.w) + bf_hi(b0.w)) +
                       (bf_lo(b1.x) + bf_hi(b1.x) + bf_lo(b1.y) + bf_hi(b1.y)) + (bf_lo(b1.z) + bf_hi(b1.z) + bf_lo(b1.w) + bf_hi(b1.w));
#pragma unroll 1
          for (int o = 1; o < 32; o <<= 1) bsum += __shfl_xor_sync(0xffffffffu, bsum, o);
          if (lane == 0) asm volatile("st.relaxed.gpu.global.u32 [%0], %1;" ::"l"(g_CS + (wi < 4 ? 0 : 512) + ch), "r"(tagf(bsum, tag)) : "memory");
        }
        mbar_wait(BAR(c, B_FULLX + 2 * it), 0);
        mbar_wait(BAR(c, B_FULLX + 2 * it + 1), 0);
        const uint4 v = lds4u(src + (it < 2 ? 2 * it + ck : 4 * it - 2 + 2 * ck) * SLOT);
        const uint32_t u[4] = {v.x, v.y, v.z, v.w};
#pragma unroll
        for (int i = 0; i < 4; i++) {
          const float lo = bf_lo(u[i]), hi = bf_hi(u[i]);
          f[8 * it + 2 * i] = lo; f[8 * it + 2 * i + 1] = hi;
          s0 += lo; s1 += hi; q0 = fmaf(lo, lo, q0); q1 = fmaf(hi, hi, q1);
        }
      }
      __syncwarp();
      if (lane < 16) mbar_arrive_cta(BAR(c, B_EMPTYX + (lane >> 1)), lane & 1, 1);
      s0 += s1; q0 += q1;
#pragma unroll
      for (int o = 1; o < 16; o <<= 1) { s0 += __shfl_xor_sync(0xffffffffu, s0, o); q0 += __shfl_xor_sync(0xffffffffu, q0, o); }
      const float mean = s0 * (1.f / D_);
      const float rs = rsqrtf(fmaxf(q0 * (1.f / D_) - mean * mean, 0.f) + 1e-5f), nm = -mean * rs;
      if ((lane & 15) == 0) st_relaxed2(g_stat + 2 * t, tagf(mean, tag), tagf(rs, tag));
      char* d = (char*)(g_xn + (size_t)t * D_) + (lane & 15) * 16;
#pragma unroll
      for (int it = 0; it < 4; it++) {
        const float* g = &f[8 * it];
        st_weak4(d + it * 256, pack_bf16(fmaf(g[0], rs, nm), fmaf(g[1], rs, nm)), pack_bf16(fmaf(g[2], rs, nm), fmaf(g[3], rs, nm)),
                 pack_bf16(fmaf(g[4], rs, nm), fmaf(g[5], rs, nm)), pack_bf16(fmaf(g[6], rs, nm), fmaf(g[7], rs, nm)));
      }
      uint32_t rbk = 0;
#pragma unroll
      for (int it = 0; it < 4; it++) rbk |= ld_relaxed((const uint32_t*)(d + it * 256));
      rbk = __reduce_or_sync(0xffffffffu, rbk);
      asm volatile("" : "+r"(rbk) :: "memory");
      if (lane == 0) asm volatile("red.relaxed.gpu.global.add.u32 [%0], 1;" ::"l"(g_cnt + c.rb * 32 + 5) : "memory");
      if (w) TSW(27);
      {
        const int n = threadIdx.x & 127;
        int it = SPIN_LIMIT;
        if (w == 1) {
          const uint32_t* src = g_stat + 2 * (c.rb * 128 + 32 * ((n >> 1) & 3) + 2 * (n >> 3) + (n & 1));
          uint2 sv;
          do { sv = ld_relaxed2(src); } while ((((sv.x ^ tag) | (sv.y ^ tag)) & 1u) && --it > 0);
          sts2(c.sb + OFF_STAT + n * 8, __uint_as_float(sv.x), __uint_as_float(sv.y));
        } else {
          const uint32_t* src = g_CS + (n >> 6) * 512 + 64 * c.j + (n & 63);
          uint32_t sv;
          do { sv = ld_relaxed(src); } while (((sv ^ tag) & 1u) && --it > 0);
          mbar_wait(BAR(c, B_EMPTYX + 5), 0);
          asm volatile("st.shared.u32 [%0], %1;" ::"r"(c.sb + cs_off((n >> 4) & 3, (n >> 6) * 16 + (n & 15))), "r"(sv) : "memory");
        }
        if (w) TSW(29);
        nb_arrive(NB_STATS, 384);
      }
      if (w == 1) {
        mbar_wait(BAR(c, B_FULLX + 5), 1);
        unsigned char* xo = g_X + (size_t)((c.rb * 4 + c.nt) * 2 + (c.q >= 2)) * SLOT + (threadIdx.x - 384) * 16;
#pragma unroll
        for (int k = 0; k < 8; k++) st_weak4(xo + k * 2048, tag ^ 1, 0, 0, 0);
      }
    }
#pragma unroll 1
    for (int job = 1 + w; job < 4; job += 2) {
      const bool hv = job == 2 && !c.heavy;
      const uint32_t rel = lane == 0 ? mapa(BAR(c, B_EMPTYR), c.hf) : mapa(BAR(c, B_EMPTYP), lane & 1);
      const uint32_t rt = lane == 0 ? (job < 3 ? 0x2103210Fu : 0xFFF3210Fu) : (job == 3 && lane < 3) ? 0x5431F0FFu : 0xFFFFFFFFu;
      nb_sync(NB_H0 + job - 1, 256);
      if (hv) {
        p1_job32(c, rel, rt, a0, a1);
        wg_wait<0>();
        pin<0, 32>(a0); pin<0, 32>(a1);
#pragma unroll
        for (int i = 0; i < 16; i++) { a0[32 + i] = a0[16 + i]; a1[32 + i] = a1[16 + i]; }
      } else {
        p1_job<1>(c, job, job == 3 && !c.heavy, rel, rt, a0, a1);
        wg_wait<0>();
        pin<0, 64>(a0); pin<0, 64>(a1);
      }
      if (job == 1) TSW(53); else if (job == 2) TSW(56); else TSW(59);
      if (job < 3 && lane == 0) mbar_arrive_addr(rel + 24);
      if (job == 2 ? (lane >= 2 && lane < 16 && (lane >> 1) != 3) : (job == 3 && (lane >> 1) == 7)) mbar_arrive_addr(rel + 8 * (lane >> 1) - 8);
      mbar_wait(BAR(c, B_STFREE + 1 + (job == 3)), job == 1);
      {
        const int i8 = lane & 7, mi = lane >> 3;
        const int sh = hv ? 6 : 7, kx = (hv ? i8 >> 1 : i8) ^ (mi >> 1);
        const uint32_t st = c.sb + SL_ST * SLOT + ((16 * warp + 8 * (mi & 1) + i8) << sh);
#pragma unroll
        for (int jj = 0; jj < 8; jj += 2) {
          if (jj == 4 && hv) break;
#pragma unroll
          for (int mt = 0; mt < 2; mt++) {
            float (&a)[64] = mt ? a1 : a0;
            uint32_t pk[4];
#pragma unroll
            for (int u = 0; u < 4; u++) {
              const int i = 4 * jj + 2 * u;
              pk[u] = mul_bf16x2(pack_relu_bf16(a[i], a[i + 1]), pack_bf16(a[32 + i], a[33 + i]));
            }
            stsm4(st + (mt << (sh + 6)) + ((jj ^ kx) << 4), pk[0], pk[1], pk[2], pk[3]);
          }
        }
      }
      fence_async_smem();
      __syncwarp();
      if (lane == 0) mbar_arrive(BAR(c, B_STFULL + 1));
      if (job == 1) TSW(55); else if (job == 2) TSW(58); else TSW(61);
    }
    if (c.q < 2) phase2<true>(p, c, w, a0); else phase2<false>(p, c, w, a0);
    nb_sync(NB_END, 256);
    if (threadIdx.x == 511) asm volatile("red.relaxed.gpu.global.add.u32 [%0], 1;" ::"l"(g_epoch + blockIdx.x * 8) : "memory");
  }
}

typedef CUresult (*EncodeFn)(CUtensorMap*, CUtensorMapDataType, cuuint32_t, void*, const cuuint64_t*, const cuuint64_t*,
                             const cuuint32_t*, const cuuint32_t*, CUtensorMapInterleave, CUtensorMapSwizzle,
                             CUtensorMapL2promotion, CUtensorMapFloatOOBfill);

void make2d(EncodeFn enc, CUtensorMap* m, const void* ptr, uint64_t inner, uint64_t outer, uint32_t bi, uint32_t bo,
            CUtensorMapSwizzle sw) {
  cuuint64_t gd[2] = {inner, outer}, gs[1] = {inner * 2};
  cuuint32_t bd[2] = {bi, bo}, es[2] = {1, 1};
  enc(m, CU_TENSOR_MAP_DATA_TYPE_BFLOAT16, 2, (void*)ptr, gd, gs, bd, es, CU_TENSOR_MAP_INTERLEAVE_NONE, sw,
      CU_TENSOR_MAP_L2_PROMOTION_L2_256B, CU_TENSOR_MAP_FLOAT_OOB_FILL_NONE);
}

}

extern "C" void kernel_launch(void* const* d_in, const int* in_sizes, int n_in, void* d_out, int out_size) {
  (void)in_sizes; (void)n_in; (void)out_size;
  static EncodeFn enc = nullptr;
  static void* xn = nullptr;
  if (!enc) {
    void* fn = nullptr;
    cudaDriverEntryPointQueryResult qr;
    cudaGetDriverEntryPoint("cuTensorMapEncodeTiled", &fn, cudaEnableDefault, &qr);
    enc = (EncodeFn)fn;
    cudaGetSymbolAddress(&xn, g_xn);
    cudaFuncSetAttribute(fused_kernel, cudaFuncAttributeMaxDynamicSharedMemorySize, SMEM_BYTES);
  }
  Params p;
  p.x = (const __nv_bfloat16*)d_in[0];
  p.lre = (const __nv_bfloat16*)d_in[1];
  p.lim = (const __nv_bfloat16*)d_in[2];
  p.bre = (const __nv_bfloat16*)d_in[3];
  p.bim = (const __nv_bfloat16*)d_in[4];
  p.cre = (const __nv_bfloat16*)d_in[5];
  p.cim = (const __nv_bfloat16*)d_in[6];
  p.logdt = (const __nv_bfloat16*)d_in[7];
  p.dskip = (const __nv_bfloat16*)d_in[8];
  p.wg = (const __nv_bfloat16*)d_in[10];
  p.wu = (const __nv_bfloat16*)d_in[11];
  p.wd = (const __nv_bfloat16*)d_in[12];
  p.out = (float*)d_out;
  p.zero = 0;
  {
    cuuint64_t gd[5] = {512, 2, 4, 16, 16}, gs[4] = {1024, 32 * 1024, 2 * 1024, 128 * 1024};
    cuuint32_t bd[5] = {64, 2, 4, 16, 1}, es[5] = {1, 1, 1, 1, 1};
    enc(&p.mX, CU_TENSOR_MAP_DATA_TYPE_BFLOAT16, 5, (void*)p.x, gd, gs, bd, es, CU_TENSOR_MAP_INTERLEAVE_NONE,
        CU_TENSOR_MAP_SWIZZLE_128B, CU_TENSOR_MAP_L2_PROMOTION_L2_256B, CU_TENSOR_MAP_FLOAT_OOB_FILL_NONE);
    bd[3] = 8;
    enc(&p.mXN, CU_TENSOR_MAP_DATA_TYPE_BFLOAT16, 5, xn, gd, gs, bd, es, CU_TENSOR_MAP_INTERLEAVE_NONE,
        CU_TENSOR_MAP_SWIZZLE_128B, CU_TENSOR_MAP_L2_PROMOTION_L2_256B, CU_TENSOR_MAP_FLOAT_OOB_FILL_NONE);
  }
  make2d(enc, &p.mW[0], p.bre, 512, 512, 64, 64, CU_TENSOR_MAP_SWIZZLE_128B);
  make2d(enc, &p.mW[1], p.bim, 512, 512, 64, 64, CU_TENSOR_MAP_SWIZZLE_128B);
  make2d(enc, &p.mW[2], p.wg, F_, 512, 64, 64, CU_TENSOR_MAP_SWIZZLE_128B);
  make2d(enc, &p.mW[3], p.wu, F_, 512, 64, 64, CU_TENSOR_MAP_SWIZZLE_128B);
  make2d(enc, &p.mW[4], p.wg, F_, 512, 32, 128, CU_TENSOR_MAP_SWIZZLE_64B);
  make2d(enc, &p.mW[5], p.wu, F_, 512, 32, 128, CU_TENSOR_MAP_SWIZZLE_64B);
  make2d(enc, &p.mC[0], p.cre, 512, 512, 64, 128, CU_TENSOR_MAP_SWIZZLE_128B);
  make2d(enc, &p.mC[1], p.cim, 512, 512, 64, 128, CU_TENSOR_MAP_SWIZZLE_128B);
  {
    cuuint64_t gd[3] = {64, F_, 8}, gs[2] = {1024, 128};
    cuuint32_t bd[3] = {64, 32, 2}, es[3] = {1, 1, 1};
    enc(&p.mWd, CU_TENSOR_MAP_DATA_TYPE_BFLOAT16, 3, (void*)p.wd, gd, gs, bd, es, CU_TENSOR_MAP_INTERLEAVE_NONE,
        CU_TENSOR_MAP_SWIZZLE_128B, CU_TENSOR_MAP_L2_PROMOTION_L2_256B, CU_TENSOR_MAP_FLOAT_OOB_FILL_NONE);
  }
  for (int i = 0; i < 22; i++) {
    const int v = i + (i >= 2), st = v % 7;
    p.sp[i] = st * 8 | ((v / 7) & 1);
    int ta, tb = -1;
    if (i >= 15 && i < 18) {
      const int ja = 3 + 2 * (i - 15);
      p.fa[i] = slice_start(ja) + 64; p.fb[i] = slice_start(ja + 1) + 64;
      ta = 16 + 3 * ja + 1; tb = i < 17 ? ta + 3 : ta;
    } else {
      const int j = i < 8 ? i : i < 15 ? i - 8 : i == 18 ? 7 : i - 19, job = i < 8 ? 0 : i < 11 ? 1 : 2;
      p.fa[i] = slice_start(j) + 64 * job - (job == 2 && j >= 3 ? 32 : 0);
      p.fb[i] = p.fa[i] + 32;
      ta = 16 + 3 * j + job;
    }
    const int rdy = i == 8 ? 8 : i == 11 ? 16 : i == 19 ? 24 : 0;
    for (int hf = 0; hf < 2; hf++) {
      p.at[hf][i] = make_int4(i * SLOT + hf * 8192, st * 2 * SLOT + hf * 8192, 0, p.sp[i]);
      p.at[2 + hf][i] = tb < 0 ? make_int4(ta * SLOT + hf * 8192, st * 2 * SLOT + hf * 8192, 0, p.sp[i] | rdy << 8)
                               : make_int4(ta * SLOT + hf * 4096, st * 2 * SLOT + hf * 4096, tb * SLOT + hf * 4096, p.sp[i] | rdy << 8);
    }
  }
  fused_kernel<<<128, 512, SMEM_BYTES>>>(p);
}
```
